```python
import torch

def _softmax(x, axis=-1):
    return torch.softmax(x, dim=axis)
def _gelu(x):
    return torch.nn.functional.gelu(x, approximate="tanh")
def _silu(x):
    return torch.nn.functional.silu(x)
def _sigmoid(x):
    return torch.sigmoid(x)
def _layernorm(x, axis=-1, eps=1e-5):
    m = x.mean(dim=axis, keepdim=True)
    v = x.var(dim=axis, keepdim=True, unbiased=False)
    return (x - m) / torch.sqrt(v + eps)
def _scatter_add(tgt, idx, src, axis=0):
    return tgt.clone().index_add_(axis, idx, src)
def _segment_sum(src, seg, n):
    out = torch.zeros((n,) + src.shape[1:], dtype=src.dtype)
    return out.index_add_(0, seg, src)
def _pad(x, pw):
    flat = tuple(v for pair in reversed(pw) for v in pair)
    return torch.nn.functional.pad(x, flat)

kernel_name = 'concat_heads__gqa_block_cached__gqa_block_cached__decode'

def setup_inputs():

    _w = (lambda a: (lambda t: t.to(torch.bfloat16) if t.is_floating_point() else t)(torch.as_tensor(a)))
    def _A_setup():
        B, Sq, D = 2, 1, 448
        Hq, Hkv, Sk, Dh = 16, 8, 4096, 256
        assert Hq % Hkv == 0, (Hq, Hkv)
        return {
            "x": _w((lambda *s: torch.randn(*s, dtype=torch.bfloat16) * 0.8)(B, Sq, D)),
            "k_cache": _w((lambda *s: torch.randn(*s, dtype=torch.bfloat16) * 0.8)(B, Hkv, Sk, Dh)),
            "v_cache": _w((lambda *s: torch.randn(*s, dtype=torch.bfloat16) * 0.05)(B, Hkv, Sk, Dh)),
            "wq": _w((lambda *s: torch.randn(*s, dtype=torch.bfloat16) * 0.8)(D, Hq * Dh) * (D ** -0.5)),
            "wo": _w((lambda *s: torch.randn(*s, dtype=torch.bfloat16) * 0.05)(Hq * Dh, D) * ((Hq * Dh) ** -0.5)),
        }
    _A_in = _A_setup()

    def _B_setup():
        B, Sq, D = 2, 1, 448
        Hq, Hkv, Sk, Dh = 16, 8, 4096, 256
        assert Hq % Hkv == 0, (Hq, Hkv)
        return {
            "x": _w((lambda *s: torch.randn(*s, dtype=torch.bfloat16) * 0.8)(B, Sq, D)),
            "k_cache": _w((lambda *s: torch.randn(*s, dtype=torch.bfloat16) * 0.8)(B, Hkv, Sk, Dh)),
            "v_cache": _w((lambda *s: torch.randn(*s, dtype=torch.bfloat16) * 0.05)(B, Hkv, Sk, Dh)),
            "wq": _w((lambda *s: torch.randn(*s, dtype=torch.bfloat16) * 0.8)(D, Hq * Dh) * (D ** -0.5)),
            "wo": _w((lambda *s: torch.randn(*s, dtype=torch.bfloat16) * 0.05)(Hq * Dh, D) * ((Hq * Dh) ** -0.5)),
        }
    _B_in = _B_setup()

    return {
        "A_x": _A_in["x"],
        "A_k_cache": _A_in["k_cache"],
        "A_v_cache": _A_in["v_cache"],
        "A_wq": _A_in["wq"],
        "A_wo": _A_in["wo"],
        "B_x": _B_in["x"],
        "B_k_cache": _B_in["k_cache"],
        "B_v_cache": _B_in["v_cache"],
        "B_wq": _B_in["wq"],
        "B_wo": _B_in["wo"],
    }

def reference(A_x, A_k_cache, A_v_cache, A_wq, A_wo, B_x, B_k_cache, B_v_cache, B_wq, B_wo):
    def _A_ref(x, k_cache, v_cache, wq, wo):
        B, Sq, D = x.shape
        Hq, Dh = 16, 256
        Hkv = k_cache.shape[1]
        rep = Hq // Hkv
        q = (lambda x, *d: x.permute(*d))((x @ wq).reshape(B, Sq, Hq, Dh), 0, 2, 1, 3)
        k = (lambda x, n, axis: torch.repeat_interleave(x, n, dim=axis))(k_cache, rep, axis=1)
        v = (lambda x, n, axis: torch.repeat_interleave(x, n, dim=axis))(v_cache, rep, axis=1)
        scores = torch.einsum("bhqd,bhkd->bhqk", q, k) * (Dh ** -0.5)
        p = _softmax(scores, axis=-1)
        o = torch.einsum("bhqk,bhkd->bhqd", p, v)
        return (lambda x, *d: x.permute(*d))(o, 0, 2, 1, 3).reshape(B, Sq, Hq * Dh) @ wo

    def _B_ref(x, k_cache, v_cache, wq, wo):
        B, Sq, D = x.shape
        Hq, Dh = 16, 256
        Hkv = k_cache.shape[1]
        rep = Hq // Hkv
        q = (lambda x, *d: x.permute(*d))((x @ wq).reshape(B, Sq, Hq, Dh), 0, 2, 1, 3)
        k = (lambda x, n, axis: torch.repeat_interleave(x, n, dim=axis))(k_cache, rep, axis=1)
        v = (lambda x, n, axis: torch.repeat_interleave(x, n, dim=axis))(v_cache, rep, axis=1)
        scores = torch.einsum("bhqd,bhkd->bhqk", q, k) * (Dh ** -0.5)
        p = _softmax(scores, axis=-1)
        o = torch.einsum("bhqk,bhkd->bhqd", p, v)
        return (lambda x, *d: x.permute(*d))(o, 0, 2, 1, 3).reshape(B, Sq, Hq * Dh) @ wo

    a = _A_ref(A_x, A_k_cache, A_v_cache, A_wq, A_wo)
    b = _B_ref(B_x, B_k_cache, B_v_cache, B_wq, B_wo)
    return torch.concatenate([a, b], axis=-1)
```

```cpp
#include <cuda_runtime.h>
#include <cuda_bf16.h>
#include <cuda.h>
#include <stdint.h>

#define RING 6
#define INFLIGHT 2
#define INIT_DEPTH 2
#define BURST 1
#define L2PROMO CU_TENSOR_MAP_L2_PROMOTION_L2_256B
#define END_DEPTH INFLIGHT
#define END_AT 33
#define PACE 1
#define PACE_T1 0
#define PACE_TILES 33
#define HOLD_FROM 4
#define HOLD_DB 32
#define HOLD_G 10
#define HOLD_MAX 1200
#define STAT_AT 8
#define GATHER_AT 15
#define L2_PREFETCH 0
#define SPIN_LIMIT (1 << 22)

namespace {

constexpr int SK = 4096;
constexpr int NCTA = 128;
constexpr int TILE_KEYS = 64;
constexpr int TILE_BYTES = TILE_KEYS * 512;
constexpr int NKT = 16;
constexpr int NTILES = 2 + 2 * NKT + 2;
constexpr int W_BYTES = 28672;
constexpr int NTHREADS = 320;

constexpr int OFF_RING = 0;
constexpr int OFF_S = OFF_RING + RING * TILE_BYTES;
constexpr int OFF_P = OFF_S + 8192;
constexpr int P_STRIDE = 2064;
constexpr int OFF_RED = OFF_P + 4224;
constexpr int OFF_Q = OFF_RED + 2048;
constexpr int OFF_B = OFF_Q + 1024 + 64;
constexpr int OFF_MISC = OFF_B + 1024;
constexpr int OFF_BAR = OFF_MISC + 256;
constexpr int SMEM_USED = OFF_BAR + 256;
constexpr int SMEM_BYTES = SMEM_USED + 1024;

struct Maps { CUtensorMap tm[8]; };

__device__ uint4 g_qin[NCTA][64];
__device__ uint4 g_stat[NCTA][4];
__device__ uint4 g_oin[NCTA][64];
__device__ uint4 g_yin[2 * 56][64 * 4];
__device__ unsigned int g_ready;
__device__ unsigned int g_progress;

#define STAMP(i) do {} while (0)

__device__ __forceinline__ uint32_t smem_u32(const void* p) { return (uint32_t)__cvta_generic_to_shared(p); }
__device__ __forceinline__ void mbar_init(uint32_t a, uint32_t c) {
    asm volatile("mbarrier.init.shared::cta.b64 [%0], %1;" ::"r"(a), "r"(c) : "memory");
}
__device__ __forceinline__ void mbar_expect_tx(uint32_t a, uint32_t b) {
    asm volatile("mbarrier.arrive.expect_tx.shared::cta.b64 _, [%0], %1;" ::"r"(a), "r"(b) : "memory");
}
__device__ __forceinline__ void mbar_arrive(uint32_t a) {
    asm volatile("mbarrier.arrive.shared::cta.b64 _, [%0];" ::"r"(a) : "memory");
}
__device__ __forceinline__ bool mbar_try(uint32_t a, uint32_t ph) {
    uint32_t ok;
    asm volatile("{\n.reg .pred p;\nmbarrier.try_wait.parity.shared::cta.b64 p, [%1], %2;\nselp.u32 %0, 1, 0, p;\n}"
                 : "=r"(ok) : "r"(a), "r"(ph) : "memory");
    return ok;
}
__device__ __forceinline__ void mbar_wait(uint32_t a, uint32_t ph) {
    int n = 0;
#pragma unroll 1
    while (!mbar_try(a, ph))
        if (++n > SPIN_LIMIT) __trap();
}
__device__ __forceinline__ uint64_t evict_first_policy() {
    uint64_t pol;
    asm volatile("createpolicy.fractional.L2::evict_first.b64 %0, 1.0;" : "=l"(pol));
    return pol;
}
__device__ __forceinline__ void tma3d(uint32_t dst, const CUtensorMap* tm, int c1, int c2, uint32_t bar, uint64_t pol) {
    asm volatile(
        "cp.async.bulk.tensor.3d.shared::cluster.global.tile.mbarrier::complete_tx::bytes.L2::cache_hint"
        " [%0], [%1, {%2, %3, %4}], [%5], %6;"
        ::"r"(dst), "l"(tm), "r"(0), "r"(c1), "r"(c2), "r"(bar), "l"(pol) : "memory");
}
__device__ __forceinline__ void ldsm4(uint32_t (&r)[4], uint32_t a) {
    asm volatile("ldmatrix.sync.aligned.m8n8.x4.shared.b16 {%0,%1,%2,%3}, [%4];"
                 : "=r"(r[0]), "=r"(r[1]), "=r"(r[2]), "=r"(r[3]) : "r"(a) : "memory");
}
__device__ __forceinline__ void ldsm4t(uint32_t (&r)[4], uint32_t a) {
    asm volatile("ldmatrix.sync.aligned.m8n8.x4.trans.shared.b16 {%0,%1,%2,%3}, [%4];"
                 : "=r"(r[0]), "=r"(r[1]), "=r"(r[2]), "=r"(r[3]) : "r"(a) : "memory");
}
__device__ __forceinline__ void mma16816(float (&c)[4], uint32_t a0, uint32_t a1, uint32_t a2, uint32_t a3,
                                         uint32_t b0, uint32_t b1) {
    asm volatile("mma.sync.aligned.m16n8k16.row.col.f32.bf16.bf16.f32 {%0,%1,%2,%3}, {%4,%5,%6,%7}, {%8,%9}, {%0,%1,%2,%3};"
                 : "+f"(c[0]), "+f"(c[1]), "+f"(c[2]), "+f"(c[3])
                 : "r"(a0), "r"(a1), "r"(a2), "r"(a3), "r"(b0), "r"(b1));
}
__device__ __forceinline__ uint4 ld_poll(const uint4* p) {
    uint4 v;
    asm volatile("ld.relaxed.gpu.global.v4.u32 {%0,%1,%2,%3}, [%4];"
                 : "=r"(v.x), "=r"(v.y), "=r"(v.z), "=r"(v.w) : "l"(p) : "memory");
    return v;
}
__device__ __forceinline__ bool has_gap(const uint4& v) { return min(min(v.x, v.y), min(v.z, v.w)) == 0u; }
__device__ __forceinline__ void poll32(const uint4* pa, const uint4* pb, uint4& a, uint4& b) {
    int n = 0;
#pragma unroll 1
    do {
        a = ld_poll(pa); b = ld_poll(pb);
        if (++n > SPIN_LIMIT) __trap();
    } while (has_gap(a) || has_gap(b));
}
__device__ __forceinline__ void st_pub(void* p, uint32_t v) {
    v = v ? v : 0x80000000u;
    asm volatile("st.relaxed.gpu.global.u32 [%0], %1;" ::"l"(p), "r"(v) : "memory");
}
__device__ __forceinline__ void st_pub_if(int pred, void* p, uint32_t v) {
    v = v ? v : 0x80000000u;
    asm volatile("{\n.reg .pred p;\nsetp.ne.s32 p, %2, 0;\n@p st.relaxed.gpu.global.u32 [%0], %1;\n}" ::"l"(p), "r"(v), "r"(pred) : "memory");
}
__device__ __forceinline__ void st_clear(uint4* p) {
    asm volatile("st.relaxed.gpu.global.v4.u32 [%0], {%1,%1,%1,%1};" ::"l"(p), "r"(0) : "memory");
}
__device__ __forceinline__ uint32_t pack_bf16(float lo, float hi) {
    uint32_t r;
    asm("cvt.rn.bf16x2.f32 %0, %1, %2;" : "=r"(r) : "f"(hi), "f"(lo));
    return r;
}
__device__ __forceinline__ uint32_t pair_rows(float lo, float hi, bool odd) {
    const float other = __shfl_xor_sync(~0u, odd ? lo : hi, 4);
    return odd ? pack_bf16(other, hi) : pack_bf16(lo, other);
}
__device__ __forceinline__ float bf_lo(uint32_t v) { return __uint_as_float(v << 16); }
__device__ __forceinline__ float bf_hi(uint32_t v) { return __uint_as_float(v & 0xffff0000u); }
__device__ __forceinline__ void bar_sync(int id, int n) { asm volatile("bar.sync %0, %1;" ::"r"(id), "r"(n) : "memory"); }
__device__ __forceinline__ void bar_arrive(int id, int n) { asm volatile("bar.arrive %0, %1;" ::"r"(id), "r"(n) : "memory"); }

constexpr float SCALE_LOG2E = 0.0625f * 1.4426950408889634f;

__global__ void __launch_bounds__(NTHREADS, 1)
gqa_decode_kernel(const __nv_bfloat16* __restrict__ wqA, const __nv_bfloat16* __restrict__ wqB,
                  const __nv_bfloat16* __restrict__ xA, const __nv_bfloat16* __restrict__ xB,
                  __nv_bfloat16* __restrict__ out, const __grid_constant__ Maps maps) {
    extern __shared__ unsigned char smem_raw[];
    const uint32_t sbase = (smem_u32(smem_raw) + 1023u) & ~1023u;
    unsigned char* sptr = smem_raw + (sbase - smem_u32(smem_raw));

    const int tid = threadIdx.x;
    const int cta = blockIdx.x;
    const int branch = cta >> 6, kvh = (cta >> 3) & 7, rank = cta & 7;
    const int batch = rank >> 2, split = rank & 3;
    const uint32_t bar_full = sbase + OFF_BAR;
    const uint32_t bar_empty = bar_full + 8 * RING;
    const uint32_t bar_stat = bar_empty + 8 * RING;
    const uint32_t bar_go = bar_stat + 8;
    const uint32_t bar_ok = bar_go + 8;
    const int row0 = ((batch * 8 + kvh) * SK) + split * 1024;
    const CUtensorMap* tm = &maps.tm[branch * 4];

    if (tid == 256) {
        STAMP(0);
        asm volatile("prefetch.tensormap [%0];" ::"l"(tm) : "memory");
        asm volatile("prefetch.tensormap [%0];" ::"l"(tm + 1) : "memory");
#pragma unroll
        for (int i = 0; i < RING; i++) { mbar_init(bar_full + 8 * i, 1); mbar_init(bar_empty + 8 * i, 8); }
        mbar_init(bar_stat, 1);
        mbar_init(bar_go, 1);
        mbar_init(bar_ok, 1);
        asm volatile("fence.mbarrier_init.release.cluster;" ::: "memory");
        const uint64_t pol = evict_first_policy();
#pragma unroll
        for (int i = 0; i < INIT_DEPTH; i++) {
            mbar_expect_tx(bar_full + 8 * i, i < 2 ? W_BYTES : TILE_BYTES);
            if (i < 2) tma3d(sbase + OFF_RING + i * TILE_BYTES, tm, i * 224, cta & 63, bar_full + 8 * i, pol);
            else tma3d(sbase + OFF_RING + i * TILE_BYTES, tm + 1, row0 + (i - 2) * TILE_KEYS, 0, bar_full + 8 * i, pol);
        }
        STAMP(1);
    }

    const int warp = tid >> 5, lane = tid & 31;
    const int grp0 = cta & ~7;
    const int g = lane >> 2, t = lane & 3;
    const bool odd = g & 1;
    const int krow = ((lane >> 4) << 3) + (lane & 7);
    const int ub = (lane >> 3) & 1;
    float* s_misc = reinterpret_cast<float*>(sptr + OFF_MISC);
    const int red = cta & 63;
    uint4* inbox = &g_yin[branch * 56 + (red < 56 ? red : 0)][0];

    float o0[4] = {0.f, 0.f, 0.f, 0.f}, o1[4] = {0.f, 0.f, 0.f, 0.f};
    float fnorm = 0.f;
    int slot = 2, ph = 0;
    unsigned ready_target = 0;

    if (warp < 8) {
        {
            const int hf = warp >> 2, mt = warp & 3;
            const uint32_t* x32 = reinterpret_cast<const uint32_t*>(branch ? xB : xA) + (g & 1) * 224 + hf * 112 + t;
            uint32_t xb[28];
#pragma unroll
            for (int k = 0; k < 28; k++) xb[k] = __ldg(x32 + 4 * k);
            bar_sync(1, NTHREADS);
            if (tid == 128) STAMP(58);
            mbar_wait(bar_full + 8 * hf, 0);
            if (tid == 128) STAMP(44);
            const uint32_t base = sbase + OFF_RING + hf * TILE_BYTES + krow * 128 + (((2 * mt + ub) ^ (lane & 7)) << 4);
            float c0[4] = {0.f, 0.f, 0.f, 0.f}, c1[4] = {0.f, 0.f, 0.f, 0.f};
#pragma unroll
            for (int k = 0; k < 14; k += 2) {
                uint32_t a[4], b[4];
                ldsm4t(a, base + k * 2048);
                ldsm4t(b, base + k * 2048 + 2048);
                mma16816(c0, a[0], a[1], a[2], a[3], xb[2 * k], xb[2 * k + 1]);
                mma16816(c1, b[0], b[1], b[2], b[3], xb[2 * k + 2], xb[2 * k + 3]);
            }
            float4* redq = reinterpret_cast<float4*>(sptr + OFF_RED) + mt * 32 + lane;
            if (hf) *redq = make_float4(c0[0] + c1[0], c0[1] + c1[1], c0[2] + c1[2], c0[3] + c1[3]);
            bar_sync(2, 256);
            if (lane == 0) { mbar_arrive(bar_empty); mbar_arrive(bar_empty + 8); }
            if (!hf) {
                const float4 o = *redq;
                const uint32_t w0 = pair_rows(c0[0] + c1[0] + o.x, c0[2] + c1[2] + o.z, odd);
                const uint32_t w1 = pair_rows(c0[1] + c1[1] + o.y, c0[3] + c1[3] + o.w, odd);
                uint32_t* dst = reinterpret_cast<uint32_t*>(&g_qin[grp0 + t][0]) + rank * 32 + mt * 8 + (odd ? 4 : 0) + (g >> 1);
                st_pub(dst, w0);
                st_pub(dst + 4 * 256, w1);
            }
            if (tid == 0) STAMP(3);
            bar_sync(4, 288);
        }
        {
            uint32_t qa[32];
            const uint32_t* q32 = reinterpret_cast<const uint32_t*>(sptr + OFF_Q + (g & 1) * 576);
#pragma unroll
            for (int k = 0; k < 16; k++) { qa[2 * k] = q32[8 * k + t]; qa[2 * k + 1] = q32[8 * k + 4 + t]; }
            const int key = warp * 8 + (lane & 7);
            const uint32_t off0 = key * 128 + ((((lane >> 3)) ^ (key & 7)) << 4);
            const uint32_t off1 = key * 128 + (((4 + (lane >> 3)) ^ (key & 7)) << 4);
            float2* sS = reinterpret_cast<float2*>(sptr + OFF_S) + (g & 1) * 512 + warp * 4 + t;
#pragma unroll 1
            for (int i = 0; i < NKT; i++) {
                mbar_wait(bar_full + 8 * slot, ph);
                const uint32_t base = sbase + OFF_RING + slot * TILE_BYTES;
                float c0[4] = {0.f, 0.f, 0.f, 0.f}, c1[4] = {0.f, 0.f, 0.f, 0.f};
                uint32_t kb[8][4];
#pragma unroll
                for (int c = 0; c < 4; c++) {
                    ldsm4(kb[2 * c], base + c * 8192 + off0);
                    ldsm4(kb[2 * c + 1], base + c * 8192 + off1);
                }
#pragma unroll
                for (int j = 0; j < 8; j++) {
                    mma16816(c0, qa[4 * j], qa[4 * j], qa[4 * j + 1], qa[4 * j + 1], kb[j][0], kb[j][1]);
                    mma16816(c1, qa[4 * j + 2], qa[4 * j + 2], qa[4 * j + 3], qa[4 * j + 3], kb[j][2], kb[j][3]);
                }
                if (g < 2) sS[i * 32] = make_float2(c0[0] + c1[0], c0[1] + c1[1]);
                __syncwarp();
                if (lane == 0) mbar_arrive(bar_empty + 8 * slot);
                if (++slot == RING) { slot = 0; ph ^= 1; }
            }
        }
        bar_sync(2, 256);
        {
            const int h = warp >> 2, j = tid & 127;
            const float4* sS = reinterpret_cast<const float4*>(sptr + OFF_S) + h * 256 + j * 2;
            const float4 a = sS[0], b = sS[1];
            float m = fmaxf(fmaxf(fmaxf(a.x, a.y), fmaxf(a.z, a.w)), fmaxf(fmaxf(b.x, b.y), fmaxf(b.z, b.w)));
#pragma unroll
            for (int o = 16; o > 0; o >>= 1) m = fmaxf(m, __shfl_xor_sync(~0u, m, o));
            if (lane == 0) s_misc[warp] = m;
            bar_sync(2, 256);
            m = fmaxf(fmaxf(s_misc[h * 4], s_misc[h * 4 + 1]), fmaxf(s_misc[h * 4 + 2], s_misc[h * 4 + 3]));
            const float mc = m * SCALE_LOG2E;
            const uint32_t p0 = pack_bf16(exp2f(fmaf(a.x, SCALE_LOG2E, -mc)), exp2f(fmaf(a.y, SCALE_LOG2E, -mc)));
            const uint32_t p1 = pack_bf16(exp2f(fmaf(a.z, SCALE_LOG2E, -mc)), exp2f(fmaf(a.w, SCALE_LOG2E, -mc)));
            const uint32_t p2 = pack_bf16(exp2f(fmaf(b.x, SCALE_LOG2E, -mc)), exp2f(fmaf(b.y, SCALE_LOG2E, -mc)));
            const uint32_t p3 = pack_bf16(exp2f(fmaf(b.z, SCALE_LOG2E, -mc)), exp2f(fmaf(b.w, SCALE_LOG2E, -mc)));
            float l = (bf_lo(p0) + bf_hi(p0)) + (bf_lo(p1) + bf_hi(p1)) + (bf_lo(p2) + bf_hi(p2)) + (bf_lo(p3) + bf_hi(p3));
            uint32_t* sP = reinterpret_cast<uint32_t*>(sptr + OFF_P + h * P_STRIDE) + (j >> 3) * 32 + (j & 7);
            sP[0] = p0; sP[8] = p1; sP[16] = p2; sP[24] = p3;
#pragma unroll
            for (int o = 16; o > 0; o >>= 1) l += __shfl_xor_sync(~0u, l, o);
            if (lane == 0) { s_misc[8 + warp] = l; if ((warp & 3) == 0) s_misc[16 + h] = m; }
            bar_sync(2, 256);
            if (tid < 16) {
                const int dstj = tid >> 2, e = tid & 3, hh = e >> 1;
                const float val = (e & 1) ? (s_misc[8 + hh * 4] + s_misc[9 + hh * 4]) + (s_misc[10 + hh * 4] + s_misc[11 + hh * 4])
                                          : s_misc[16 + hh];
                mbar_wait(bar_ok, 0);
                st_pub(reinterpret_cast<uint32_t*>(&g_stat[grp0 + batch * 4 + dstj][split]) + e, __float_as_uint(val));
            }
            __syncwarp();
            if (tid == 0) STAMP(5);
        }
        {
            const int u0 = (warp & 1) * 4 + ub;
            const uint32_t offa = (warp >> 1) * 8192 + krow * 128 + ((u0 ^ (lane & 7)) << 4);
            const uint32_t offb = (warp >> 1) * 8192 + krow * 128 + (((u0 + 2) ^ (lane & 7)) << 4);
            const uint4* sP = reinterpret_cast<const uint4*>(sptr + OFF_P + (g & 1) * P_STRIDE + t * 32);
#pragma unroll 1
            for (int i = 0; i < NKT; i++) {
                const uint4 pa = sP[i * 8], pb = sP[i * 8 + 1];
                if (i == NKT - 1) { mbar_wait(bar_stat, 0); fnorm = s_misc[32 + (t & 1)]; }
                mbar_wait(bar_full + 8 * slot, ph);
                const uint32_t base = sbase + OFF_RING + slot * TILE_BYTES;
                uint32_t va[8][4];
#pragma unroll
                for (int ks = 0; ks < 4; ks++) {
                    ldsm4t(va[2 * ks], base + ks * 2048 + offa);
                    ldsm4t(va[2 * ks + 1], base + ks * 2048 + offb);
                }
                const uint32_t pp[8] = {pa.x, pa.y, pa.z, pa.w, pb.x, pb.y, pb.z, pb.w};
#pragma unroll
                for (int ks = 0; ks < 4; ks++) {
                    mma16816(o0, va[2 * ks][0], va[2 * ks][1], va[2 * ks][2], va[2 * ks][3], pp[2 * ks], pp[2 * ks + 1]);
                    mma16816(o1, va[2 * ks + 1][0], va[2 * ks + 1][1], va[2 * ks + 1][2], va[2 * ks + 1][3], pp[2 * ks], pp[2 * ks + 1]);
                }
                __syncwarp();
                if (lane == 0) mbar_arrive(bar_empty + 8 * slot);
                if (tid == 0 && (i == STAT_AT || i == GATHER_AT)) mbar_arrive(bar_go);
                if (++slot == RING) { slot = 0; ph ^= 1; }
            }
        }
    } else if (warp == 8) {
        __syncwarp();
        bar_arrive(1, NTHREADS);
        if (lane == 0) {
            asm volatile("prefetch.tensormap [%0];" ::"l"(tm + 2) : "memory");
            asm volatile("prefetch.tensormap [%0];" ::"l"(tm + 3) : "memory");
            const uint64_t pol = evict_first_policy();
            int issued = INIT_DEPTH;
            slot = INIT_DEPTH % RING; ph = (INIT_DEPTH / RING) & 1;
            int lslot = 0, lph = 0;
            int depth = INFLIGHT, hold = 0;
#pragma unroll 1
            for (int landed = 0; issued < NTILES;) {
                mbar_wait(bar_full + 8 * lslot, lph);
                STAMP(8 + landed);
                landed++;
                if (++lslot == RING) { lslot = 0; lph ^= 1; }
                if (landed >= END_AT) depth = max(depth, END_DEPTH);
                if (hold > 0) {
                    const long long t0 = clock64();
                    while (clock64() - t0 < hold) {}
                }
#pragma unroll 1
                while (issued < ((landed + depth) & ~(BURST - 1)) && issued < NTILES) {
                    if (issued >= RING) mbar_wait(bar_empty + 8 * slot, ph ^ 1);
                    const bool kv = issued < 2 + 2 * NKT;
                    mbar_expect_tx(bar_full + 8 * slot, kv ? TILE_BYTES : W_BYTES);
                    tma3d(sbase + OFF_RING + slot * TILE_BYTES, tm + (kv ? (issued < 2 + NKT ? 1 : 2) : 3),
                          kv ? row0 + ((issued - 2) & (NKT - 1)) * TILE_KEYS : (cta & 63) * 64 + (issued - 2 - 2 * NKT) * 32,
                          0, bar_full + 8 * slot, pol);
                    issued++;
                    if (++slot == RING) { slot = 0; ph ^= 1; }
                }
                if (landed <= PACE_TILES) {
                    const int total = (int)atomicInc(&g_progress, NCTA * PACE_TILES - 1);
                    const int lag = total - landed * NCTA;
                    depth = INFLIGHT + (lag > PACE_T1);
                    hold = landed >= HOLD_FROM ? min((-lag - HOLD_DB) * HOLD_G, HOLD_MAX) : 0;
                }
            }
            STAMP(2);
        }
        return;
    } else {
        bar_arrive(1, NTHREADS);
        uint4 v0 = ld_poll(&g_qin[cta][lane]), v1 = ld_poll(&g_qin[cta][32 + lane]);
#pragma unroll
        for (int j = 0; j < 8; j++)
            if (red < 56) st_clear(inbox + j * 32 + lane);
        st_clear(&g_oin[cta][lane]); st_clear(&g_oin[cta][32 + lane]);
        if (lane < 4) st_clear(&g_stat[cta][lane]);
        if (has_gap(v0) || has_gap(v1)) poll32(&g_qin[cta][lane], &g_qin[cta][32 + lane], v0, v1);
        *reinterpret_cast<uint4*>(sptr + OFF_Q + lane * 16) = v0;
        *reinterpret_cast<uint4*>(sptr + OFF_Q + 576 + lane * 16) = v1;
        __syncwarp();
        bar_arrive(4, 288);
        if (lane == 0) STAMP(46);
        __threadfence();
        __syncwarp();
        if (lane == 0) ready_target = (atomicAdd(&g_ready, 1u) & ~(unsigned)(NCTA - 1)) + NCTA;
        st_clear(&g_qin[cta][lane]); st_clear(&g_qin[cta][32 + lane]);
    }

    int live = warp < 8;
    asm volatile("" : "+r"(live));
    {
        const int h = t & 1, mt = t >> 1;
        const float lo = (mt ? (h ? o1[1] : o1[0]) : (h ? o0[1] : o0[0])) * fnorm;
        const float hi = (mt ? (h ? o1[3] : o1[2]) : (h ? o0[3] : o0[2])) * fnorm;
        const uint32_t word = pair_rows(lo, hi, odd);
        const int pj = (warp & 1) * 16 + mt * 8 + (odd ? 4 : 0) + (g >> 1);
        const int widx = rank * 32 + (pj & 3) * 8 + (pj >> 3) * 2 + ((pj >> 2) & 1);
        st_pub_if(live, reinterpret_cast<uint32_t*>(&g_oin[grp0 + h * 4 + ((warp >> 1) & 3)][0]) + widx, word);
    }
    if (tid == 0) STAMP(49);
    if (warp != 7) {
        float y[4][4];
#pragma unroll
        for (int i = 0; i < 4; i++) { y[i][0] = y[i][1] = y[i][2] = y[i][3] = 0.f; }
        const uint32_t woff = sbase + OFF_RING + (warp & 7) * 4096 + krow * 128;
        const bool todd = t & 1;
        uint32_t* dst = reinterpret_cast<uint32_t*>(&g_yin[branch * 56 + (warp & 7) * 8 + (t >> 1)][0]) + red * 16 + g + (todd ? 8 : 0);
        uint32_t wa[16][4];
#pragma unroll
        for (int hf = 0; hf < 2; hf++) {
            if (live) mbar_wait(bar_full + 8 * slot, ph);
            if (tid == 0) STAMP(51 + hf);
#pragma unroll
            for (int k = 0; k < 8; k++)
                ldsm4t(wa[hf * 8 + k], woff + slot * TILE_BYTES + (k >> 2) * 2048 + (((2 * (k & 3) + ub) ^ (lane & 7)) << 4));
            if (++slot == RING) { slot = 0; ph ^= 1; }
        }
        if (live) bar_sync(3, 256);
        const uint4* sB = reinterpret_cast<const uint4*>(sptr + OFF_B);
        const uint4 b0 = sB[lane], b1 = sB[32 + lane];
        const uint32_t bb[8] = {b0.x, b0.y, b0.z, b0.w, b1.x, b1.y, b1.z, b1.w};
#pragma unroll
        for (int k = 0; k < 16; k++)
            mma16816(y[k & 3], wa[k][0], wa[k][1], wa[k][2], wa[k][3], bb[2 * (k >> 2)], bb[2 * (k >> 2) + 1]);
#pragma unroll
        for (int i = 0; i < 4; i++) {
            const float v0 = y[i][0] + y[i][1], v1 = y[i][2] + y[i][3];
            const float val = (todd ? v1 : v0) + __shfl_xor_sync(~0u, todd ? v0 : v1, 1);
            st_pub_if(live, dst + i * 2 * 1024, __float_as_uint(val));
        }
        if (tid == 0) STAMP(53);
    }
    if (live) return;
    if (lane == 0) STAMP(47);

    int npass = 2;
    asm volatile("" : "+r"(npass));
#pragma unroll 1
    for (int pass = 0; pass < npass; pass++) {
        if (pass) {
            if (lane == 0) {
                STAMP(48);
                int n = 0;
                unsigned v;
#pragma unroll 1
                while (true) {
                    asm volatile("ld.acquire.gpu.global.u32 %0, [%1];" : "=r"(v) : "l"(&g_ready) : "memory");
                    if ((int)(v - ready_target) >= 0) break;
                    if (++n > SPIN_LIMIT) __trap();
                    __nanosleep(500);
                }
                mbar_arrive(bar_ok);
                STAMP(59);
            }
            __syncwarp();
            mbar_wait(bar_go, 0);
            uint4 v, vv;
            poll32(&g_stat[cta][t], &g_stat[cta][t], v, vv);
            const float m0 = __uint_as_float(v.x), l0 = __uint_as_float(v.y);
            const float m1 = __uint_as_float(v.z), l1 = __uint_as_float(v.w);
            float M0 = fmaxf(m0, __shfl_xor_sync(~0u, m0, 1)); M0 = fmaxf(M0, __shfl_xor_sync(~0u, M0, 2));
            float M1 = fmaxf(m1, __shfl_xor_sync(~0u, m1, 1)); M1 = fmaxf(M1, __shfl_xor_sync(~0u, M1, 2));
            const float w0 = exp2f((m0 - M0) * SCALE_LOG2E), w1 = exp2f((m1 - M1) * SCALE_LOG2E);
            float L0 = w0 * l0, L1 = w1 * l1;
            L0 += __shfl_xor_sync(~0u, L0, 1); L0 += __shfl_xor_sync(~0u, L0, 2);
            L1 += __shfl_xor_sync(~0u, L1, 1); L1 += __shfl_xor_sync(~0u, L1, 2);
            if (lane == split) {
                s_misc[32] = w0 / L0; s_misc[33] = w1 / L1;
                mbar_arrive(bar_stat);
            }
            mbar_wait(bar_go, 1);
        }
        {
            uint4 b0 = make_uint4(0, 0, 0, 0), b1 = b0;
            if (pass) poll32(&g_oin[cta][lane * 2], &g_oin[cta][lane * 2 + 1], b0, b1);
            uint4* sB = reinterpret_cast<uint4*>(sptr + OFF_B);
            sB[lane] = b0; sB[32 + lane] = b1;
            __syncwarp();
            if (pass) {
                bar_arrive(3, 256);
                if (lane == 0) STAMP(50);
            }
        }
        const bool reduce = pass && red < 56;
        uint4 v[8];
#pragma unroll
        for (int j = 0; j < 8; j++) v[j] = make_uint4(!reduce, 1, 1, 1);
        int n = 0;
#pragma unroll 1
        while (true) {
            bool again = false;
#pragma unroll
            for (int j = 0; j < 8; j++)
                if (has_gap(v[j])) { v[j] = ld_poll(inbox + j * 32 + lane); again = true; }
            if (!__any_sync(~0u, again)) break;
            if (++n > SPIN_LIMIT) __trap();
        }
        if (lane == 0 && pass) STAMP(6);
        float a0 = 0.f, a1 = 0.f, a2 = 0.f, a3 = 0.f;
#pragma unroll
        for (int j = 0; j < 8; j++) {
            a0 += __uint_as_float(v[j].x); a1 += __uint_as_float(v[j].y);
            a2 += __uint_as_float(v[j].z); a3 += __uint_as_float(v[j].w);
        }
#pragma unroll
        for (int o = 4; o < 32; o <<= 1) {
            a0 += __shfl_xor_sync(~0u, a0, o); a1 += __shfl_xor_sync(~0u, a1, o);
            a2 += __shfl_xor_sync(~0u, a2, o); a3 += __shfl_xor_sync(~0u, a3, o);
        }
        if (reduce && lane < 4)
            asm volatile("st.global.v2.u32 [%0], {%1,%2};" ::"l"(out + (red & 1) * 896 + branch * 448 + (red >> 1) * 16 + lane * 4),
                         "r"(pack_bf16(a0, a1)), "r"(pack_bf16(a2, a3)) : "memory");
        if (lane == 0 && reduce) STAMP(7);
    }
}

typedef CUresult (*EncodeFn)(CUtensorMap*, CUtensorMapDataType, cuuint32_t, void*, const cuuint64_t*,
                             const cuuint64_t*, const cuuint32_t*, const cuuint32_t*, CUtensorMapInterleave,
                             CUtensorMapSwizzle, CUtensorMapL2promotion, CUtensorMapFloatOOBfill);

void encode_map(EncodeFn fn, CUtensorMap* tm, const void* base, uint64_t rows, uint32_t chunks,
                uint32_t box_rows, uint32_t box_chunks) {
    cuuint64_t dims[3] = {64, rows, chunks};
    cuuint64_t strides[2] = {(cuuint64_t)chunks * 128, 128};
    cuuint32_t box[3] = {64, box_rows, box_chunks};
    cuuint32_t es[3] = {1, 1, 1};
    fn(tm, CU_TENSOR_MAP_DATA_TYPE_BFLOAT16, 3, const_cast<void*>(base), dims, strides, box, es,
       CU_TENSOR_MAP_INTERLEAVE_NONE, CU_TENSOR_MAP_SWIZZLE_128B, L2PROMO,
       CU_TENSOR_MAP_FLOAT_OOB_FILL_NONE);
}

}

extern "C" void kernel_launch(void* const* d_in, const int* in_sizes, int n_in, void* d_out, int out_size) {
    (void)in_sizes; (void)n_in; (void)out_size;
    static EncodeFn encode = nullptr;
    if (!encode) {
        void* fn = nullptr;
        cudaDriverEntryPointQueryResult st;
        cudaGetDriverEntryPoint("cuTensorMapEncodeTiled", &fn, cudaEnableDefault, &st);
        encode = reinterpret_cast<EncodeFn>(fn);
        cudaFuncSetAttribute(gqa_decode_kernel, cudaFuncAttributeMaxDynamicSharedMemorySize, SMEM_BYTES);
    }
    Maps m;
    for (int br = 0; br < 2; br++) {
        encode_map(encode, &m.tm[br * 4 + 0], d_in[br * 5 + 3], 448, 64, 224, 1);
        encode_map(encode, &m.tm[br * 4 + 1], d_in[br * 5 + 1], 2 * 8 * SK, 4, TILE_KEYS, 4);
        encode_map(encode, &m.tm[br * 4 + 2], d_in[br * 5 + 2], 2 * 8 * SK, 4, TILE_KEYS, 4);
        encode_map(encode, &m.tm[br * 4 + 3], d_in[br * 5 + 4], 4096, 7, 32, 7);
    }
    gqa_decode_kernel<<<NCTA, NTHREADS, SMEM_BYTES>>>(
        static_cast<const __nv_bfloat16*>(d_in[3]), static_cast<const __nv_bfloat16*>(d_in[8]),
        static_cast<const __nv_bfloat16*>(d_in[0]), static_cast<const __nv_bfloat16*>(d_in[5]),
        static_cast<__nv_bfloat16*>(d_out), m);
}
```

```cpp
#include <cuda_runtime.h>
#include <cuda_bf16.h>
#include <cuda.h>
#include <stdint.h>

namespace {

constexpr int SK = 4096;
constexpr int NCTA = 128;
constexpr int RING = 6;
constexpr int INFLIGHT = 2;
constexpr int TILE_KEYS = 64;
constexpr int TILE_BYTES = TILE_KEYS * 512;
constexpr int NKT = 16;
constexpr int NTILES = 2 + 2 * NKT + 2;
constexpr int WQ_BYTES = 224 * 128;
constexpr int PACE_TILES = NTILES - 3;
constexpr int STAT_AT = 8;
constexpr int NTHREADS = 320;
constexpr int SPIN_LIMIT = 1 << 22;
constexpr int HOLD_G = 10, HOLD_DB = 32, HOLD_MAX = 800;
constexpr int LAG_T = 0;
constexpr int WO_TIMEOUT = 3000;

constexpr int OFF_RING = 0;
constexpr int OFF_S = OFF_RING + RING * TILE_BYTES;
constexpr int OFF_P = OFF_S + 8192;
constexpr int P_STRIDE = 2064;
constexpr int OFF_RED = OFF_P + 4224;
constexpr int OFF_Q = OFF_RED + 2048;
constexpr int OFF_B = OFF_Q + 1024 + 64;
constexpr int OFF_MISC = OFF_B + 1024;
constexpr int OFF_BAR = OFF_MISC + 256;
constexpr int SMEM_BYTES = OFF_BAR + 256 + 1024;

struct Maps { CUtensorMap tm[10]; };

__device__ uint4 g_qin[NCTA][64];
__device__ uint4 g_stat[NCTA][4];
__device__ uint4 g_oin[NCTA][64];
__device__ __align__(256) float4 g_yacc[154 * 16];
__device__ unsigned int g_ready;
__device__ unsigned int g_progress;

__device__ __forceinline__ uint32_t smem_u32(const void* p) { return (uint32_t)__cvta_generic_to_shared(p); }
__device__ __forceinline__ void mbar_init(uint32_t a, uint32_t c) {
    asm volatile("mbarrier.init.shared::cta.b64 [%0], %1;" ::"r"(a), "r"(c) : "memory");
}
__device__ __forceinline__ void mbar_expect_tx(uint32_t a, uint32_t b) {
    asm volatile("mbarrier.arrive.expect_tx.shared::cta.b64 _, [%0], %1;" ::"r"(a), "r"(b) : "memory");
}
__device__ __forceinline__ void mbar_arrive(uint32_t a) {
    asm volatile("mbarrier.arrive.shared::cta.b64 _, [%0];" ::"r"(a) : "memory");
}
__device__ __forceinline__ bool mbar_try(uint32_t a, uint32_t ph) {
    uint32_t ok;
    asm volatile("{\n.reg .pred p;\nmbarrier.try_wait.parity.shared::cta.b64 p, [%1], %2;\nselp.u32 %0, 1, 0, p;\n}"
                 : "=r"(ok) : "r"(a), "r"(ph) : "memory");
    return ok;
}
__device__ __forceinline__ bool mbar_test(uint32_t a, uint32_t ph) {
    uint32_t ok;
    asm volatile("{\n.reg .pred p;\nmbarrier.test_wait.parity.shared::cta.b64 p, [%1], %2;\nselp.u32 %0, 1, 0, p;\n}"
                 : "=r"(ok) : "r"(a), "r"(ph) : "memory");
    return ok;
}
__device__ __forceinline__ void mbar_wait(uint32_t a, uint32_t ph) {
    int n = 0;
#pragma unroll 1
    while (!mbar_try(a, ph))
        if (++n > SPIN_LIMIT) __trap();
}
__device__ __forceinline__ void spin_clocks(int n) {
    const uint32_t t0 = clock();
    while ((int)(clock() - t0) < n) {}
}
__device__ __forceinline__ uint64_t evict_first_policy() {
    uint64_t pol;
    asm volatile("createpolicy.fractional.L2::evict_first.b64 %0, 1.0;" : "=l"(pol));
    return pol;
}
__device__ __forceinline__ void tma3d(uint32_t dst, const CUtensorMap* tm, int c1, int c2, uint32_t bar, uint64_t pol) {
    asm volatile(
        "cp.async.bulk.tensor.3d.shared::cluster.global.tile.mbarrier::complete_tx::bytes.L2::cache_hint"
        " [%0], [%1, {%2, %3, %4}], [%5], %6;"
        ::"r"(dst), "l"(tm), "r"(0), "r"(c1), "r"(c2), "r"(bar), "l"(pol) : "memory");
}
__device__ __forceinline__ void ldsm4(uint32_t (&r)[4], uint32_t a) {
    asm volatile("ldmatrix.sync.aligned.m8n8.x4.shared.b16 {%0,%1,%2,%3}, [%4];"
                 : "=r"(r[0]), "=r"(r[1]), "=r"(r[2]), "=r"(r[3]) : "r"(a) : "memory");
}
__device__ __forceinline__ void ldsm4t(uint32_t (&r)[4], uint32_t a) {
    asm volatile("ldmatrix.sync.aligned.m8n8.x4.trans.shared.b16 {%0,%1,%2,%3}, [%4];"
                 : "=r"(r[0]), "=r"(r[1]), "=r"(r[2]), "=r"(r[3]) : "r"(a) : "memory");
}
__device__ __forceinline__ void mma16816(float (&c)[4], uint32_t a0, uint32_t a1, uint32_t a2, uint32_t a3,
                                         uint32_t b0, uint32_t b1) {
    asm volatile("mma.sync.aligned.m16n8k16.row.col.f32.bf16.bf16.f32 {%0,%1,%2,%3}, {%4,%5,%6,%7}, {%8,%9}, {%0,%1,%2,%3};"
                 : "+f"(c[0]), "+f"(c[1]), "+f"(c[2]), "+f"(c[3])
                 : "r"(a0), "r"(a1), "r"(a2), "r"(a3), "r"(b0), "r"(b1));
}
__device__ __forceinline__ uint4 lds128(uint32_t a) {
    uint4 v;
    asm volatile("ld.shared.v4.u32 {%0,%1,%2,%3}, [%4];" : "=r"(v.x), "=r"(v.y), "=r"(v.z), "=r"(v.w) : "r"(a) : "memory");
    return v;
}
__device__ __forceinline__ void sts128(uint32_t a, const uint4& v) {
    asm volatile("st.shared.v4.u32 [%0], {%1,%2,%3,%4};" ::"r"(a), "r"(v.x), "r"(v.y), "r"(v.z), "r"(v.w) : "memory");
}
__device__ __forceinline__ uint4 ld_poll(const uint4* p) {
    uint4 v;
    asm volatile("ld.relaxed.gpu.global.v4.u32 {%0,%1,%2,%3}, [%4];"
                 : "=r"(v.x), "=r"(v.y), "=r"(v.z), "=r"(v.w) : "l"(p) : "memory");
    return v;
}
__device__ __forceinline__ bool has_gap(const uint4& v) { return min(min(v.x, v.y), min(v.z, v.w)) == 0u; }
__device__ __forceinline__ void poll32(const uint4* pa, const uint4* pb, uint4& a, uint4& b) {
    int n = 0;
#pragma unroll 1
    do {
        a = ld_poll(pa); b = ld_poll(pb);
        if (++n > SPIN_LIMIT) __trap();
    } while (has_gap(a) || has_gap(b));
}
__device__ __forceinline__ void st_pub(void* p, uint32_t v) {
    v = v ? v : 0x80000000u;
    asm volatile("st.relaxed.gpu.global.u32 [%0], %1;" ::"l"(p), "r"(v) : "memory");
}
__device__ __forceinline__ void st_clear(uint4* p) {
    asm volatile("st.relaxed.gpu.global.v4.u32 [%0], {%1,%1,%1,%1};" ::"l"(p), "r"(0) : "memory");
}
__device__ __forceinline__ void atom_add4(float4& old, float4* p, float a, float b, float c) {
    asm volatile("atom.relaxed.gpu.global.add.v4.f32 {%0,%1,%2,%3}, [%4], {%5,%6,%7,%8};"
                 : "=f"(old.x), "=f"(old.y), "=f"(old.z), "=f"(old.w) : "l"(p), "f"(a), "f"(b), "f"(c), "f"(1.0f) : "memory");
}
__device__ __forceinline__ void st_bf16(__nv_bfloat16* p, float v) {
    asm volatile("st.global.u16 [%0], %1;" ::"l"(p), "h"(__bfloat16_as_ushort(__float2bfloat16(v))) : "memory");
}
__device__ __forceinline__ uint32_t pack_bf16(float lo, float hi) {
    uint32_t r;
    asm("cvt.rn.bf16x2.f32 %0, %1, %2;" : "=r"(r) : "f"(hi), "f"(lo));
    return r;
}
__device__ __forceinline__ uint32_t pair_rows(float lo, float hi, bool odd) {
    const float other = __shfl_xor_sync(~0u, odd ? lo : hi, 4);
    return odd ? pack_bf16(other, hi) : pack_bf16(lo, other);
}
__device__ __forceinline__ float bf_lo(uint32_t v) { return __uint_as_float(v << 16); }
__device__ __forceinline__ float bf_hi(uint32_t v) { return __uint_as_float(v & 0xffff0000u); }
__device__ __forceinline__ void bar_sync(int id, int n) { asm volatile("bar.sync %0, %1;" ::"r"(id), "r"(n) : "memory"); }
__device__ __forceinline__ void bar_arrive(int id, int n) { asm volatile("bar.arrive %0, %1;" ::"r"(id), "r"(n) : "memory"); }

constexpr float SCALE_LOG2E = 0.0625f * 1.4426950408889634f;

__global__ void __launch_bounds__(NTHREADS, 1)
gqa_decode_kernel(const __nv_bfloat16* __restrict__ xA, const __nv_bfloat16* __restrict__ xB,
                  __nv_bfloat16* __restrict__ out,
                  const __grid_constant__ Maps maps) {
    extern __shared__ unsigned char smem_raw[];
    const uint32_t sbase = (smem_u32(smem_raw) + 1023u) & ~1023u;
    unsigned char* sptr = smem_raw + (sbase - smem_u32(smem_raw));

    const int tid = threadIdx.x;
    const int cta = blockIdx.x;
    const int branch = cta >> 6, kvh = (cta >> 3) & 7, rank = cta & 7;
    const int batch = rank >> 2, split = rank & 3;
    const uint32_t bar_full = sbase + OFF_BAR;
    const uint32_t bar_empty = bar_full + 8 * RING;
    const uint32_t bar_stat = bar_empty + 8 * RING;
    const uint32_t bar_go = bar_stat + 8;
    const uint32_t bar_ok = bar_go + 8;
    const uint32_t bar_b = bar_ok + 8;
    const CUtensorMap* tm = &maps.tm[branch * 5];

    if (tid == 256) {
        mbar_init(bar_full, 1);
        mbar_init(bar_full + 8, 1);
        asm volatile("fence.mbarrier_init.release.cluster;" ::: "memory");
        const uint64_t pol = evict_first_policy();
#pragma unroll
        for (int i = 0; i < 2; i++) {
            mbar_expect_tx(bar_full + 8 * i, WQ_BYTES);
            tma3d(sbase + OFF_RING + i * TILE_BYTES, tm, i * 224, cta & 63, bar_full + 8 * i, pol);
        }
#pragma unroll
        for (int i = 0; i < RING; i++) { if (i >= 2) mbar_init(bar_full + 8 * i, 1); mbar_init(bar_empty + 8 * i, 8); }
        mbar_init(bar_stat, 1);
        mbar_init(bar_go, 1);
        mbar_init(bar_ok, 1);
        mbar_init(bar_b, 1);
        asm volatile("fence.mbarrier_init.release.cluster;" ::: "memory");
    }

    const int warp = tid >> 5, lane = tid & 31;
    const int grp0 = cta & ~7;
    const int g = lane >> 2, t = lane & 3;
    float* s_misc = reinterpret_cast<float*>(sptr + OFF_MISC);
    int slot = 2, ph = 0;

    if (warp == 8) {
        __syncwarp();
        bar_arrive(1, NTHREADS);
        if (lane == 0) {
            const uint64_t pol = evict_first_policy();
            const int row0 = ((batch * 8 + kvh) * SK) + split * 1024;
            const int swap = split >> 1;
            int issued = 2;
            int lslot = 0, lph = 0;
            int total = 0;
            int hold = 0;
#pragma unroll 1
            for (int landed = 0; landed < PACE_TILES;) {
                mbar_wait(bar_full + 8 * lslot, lph);
                const int lag = total - landed * NCTA;
                const int depth = INFLIGHT + (lag > LAG_T);
                hold = min((-lag - HOLD_DB) * HOLD_G, HOLD_MAX);
                landed++;
                if (++lslot == RING) { lslot = 0; lph ^= 1; }
                if (landed > 4 && issued < 2 + 2 * NKT) spin_clocks(hold);
#pragma unroll 1
                while (issued < landed + depth && issued < 2 + 2 * NKT) {
                    if (issued >= RING) mbar_wait(bar_empty + 8 * slot, ph ^ 1);
                    mbar_expect_tx(bar_full + 8 * slot, TILE_BYTES);
                    tma3d(sbase + OFF_RING + slot * TILE_BYTES, tm + (issued < 2 + NKT ? 1 : 2),
                          row0 + (((issued - 2) & (NKT - 1)) ^ swap) * TILE_KEYS, 0, bar_full + 8 * slot, pol);
                    issued++;
                    if (++slot == RING) { slot = 0; ph ^= 1; }
                }
                total = (int)atomicInc(&g_progress, NCTA * PACE_TILES - 1);
            }
            const uint32_t t0 = clock();
#pragma unroll 1
            for (int k = 0; k < 2; k++) {
                const int limit = k ? WO_TIMEOUT : hold;
                while ((int)(clock() - t0) < limit && !mbar_test(bar_full + 8 * lslot, lph)) {}
                mbar_wait(bar_empty + 8 * slot, ph ^ 1);
                mbar_expect_tx(bar_full + 8 * slot, k ? 3 * 8192 : TILE_BYTES);
                tma3d(sbase + OFF_RING + slot * TILE_BYTES, tm + 3 + k, (cta & 63) * 64, k * 4, bar_full + 8 * slot, pol);
                if (++slot == RING) { slot = 0; ph ^= 1; }
            }
        }
        return;
    }
    if (warp == 9) {
        bar_sync(1, NTHREADS);
        uint4 v0 = ld_poll(&g_qin[cta][lane]), v1 = ld_poll(&g_qin[cta][32 + lane]);
        if (lane < 4 || (lane < 8 && cta < 154 - NCTA))
            st_clear(reinterpret_cast<uint4*>(g_yacc) + (cta + (lane >> 2) * NCTA) * 16 + (lane & 3));
        st_clear(&g_oin[cta][lane]); st_clear(&g_oin[cta][32 + lane]);
        if (lane < 4) st_clear(&g_stat[cta][lane]);
        if (has_gap(v0) || has_gap(v1)) poll32(&g_qin[cta][lane], &g_qin[cta][32 + lane], v0, v1);
        *reinterpret_cast<uint4*>(sptr + OFF_Q + lane * 16) = v0;
        *reinterpret_cast<uint4*>(sptr + OFF_Q + 576 + lane * 16) = v1;
        __syncwarp();
        bar_arrive(4, 288);
        __threadfence();
        __syncwarp();
        unsigned ready_target = 0;
        if (lane == 0) ready_target = (atomicAdd(&g_ready, 1u) & ~(unsigned)(NCTA - 1)) + NCTA;
        st_clear(&g_qin[cta][lane]); st_clear(&g_qin[cta][32 + lane]);
        if (lane == 0) {
            int n = 0;
#pragma unroll 1
            while (true) {
                unsigned v;
                asm volatile("ld.acquire.gpu.global.u32 %0, [%1];" : "=r"(v) : "l"(&g_ready) : "memory");
                if ((int)(v - ready_target) >= 0) break;
                if (++n > SPIN_LIMIT) __trap();
                __nanosleep(500);
            }
            mbar_arrive(bar_ok);
        }
        __syncwarp();
        mbar_wait(bar_go, 0);
        uint4 v, vv;
        poll32(&g_stat[cta][t], &g_stat[cta][t], v, vv);
        const float m0 = __uint_as_float(v.x), l0 = __uint_as_float(v.y);
        const float m1 = __uint_as_float(v.z), l1 = __uint_as_float(v.w);
        float M0 = fmaxf(m0, __shfl_xor_sync(~0u, m0, 1)); M0 = fmaxf(M0, __shfl_xor_sync(~0u, M0, 2));
        float M1 = fmaxf(m1, __shfl_xor_sync(~0u, m1, 1)); M1 = fmaxf(M1, __shfl_xor_sync(~0u, M1, 2));
        const float w0 = exp2f((m0 - M0) * SCALE_LOG2E), w1 = exp2f((m1 - M1) * SCALE_LOG2E);
        float L0 = w0 * l0, L1 = w1 * l1;
        L0 += __shfl_xor_sync(~0u, L0, 1); L0 += __shfl_xor_sync(~0u, L0, 2);
        L1 += __shfl_xor_sync(~0u, L1, 1); L1 += __shfl_xor_sync(~0u, L1, 2);
        if (lane == split) {
            s_misc[32] = w0 / L0; s_misc[33] = w1 / L1;
            mbar_arrive(bar_stat);
        }
        mbar_wait(bar_go, 1);
        poll32(&g_oin[cta][lane * 2], &g_oin[cta][lane * 2 + 1], v0, v1);
        sts128(sbase + OFF_B + lane * 16, v0);
        sts128(sbase + OFF_B + 512 + lane * 16, v1);
        __syncwarp();
        if (lane == 0) mbar_arrive(bar_b);
        return;
    }

    const bool odd = g & 1, todd = t & 1;
    const int krow = ((lane >> 4) << 3) + (lane & 7);
    const int ub = (lane >> 3) & 1;
    {
        const int hf = warp >> 2, mt = warp & 3;
        const uint32_t* x32 = reinterpret_cast<const uint32_t*>(branch ? xB : xA) + (g & 1) * 224 + hf * 112 + t;
        uint32_t xb[28];
#pragma unroll
        for (int k = 0; k < 28; k++) xb[k] = __ldg(x32 + 4 * k);
        bar_sync(1, NTHREADS);
        mbar_wait(bar_full + 8 * hf, 0);
        const uint32_t base = sbase + OFF_RING + hf * TILE_BYTES + krow * 128 + (((2 * mt + ub) ^ (lane & 7)) << 4);
        float c0[4] = {0.f, 0.f, 0.f, 0.f}, c1[4] = {0.f, 0.f, 0.f, 0.f};
#pragma unroll
        for (int k = 0; k < 14; k += 2) {
            uint32_t a[4], b[4];
            ldsm4t(a, base + k * 2048);
            ldsm4t(b, base + k * 2048 + 2048);
            mma16816(c0, a[0], a[1], a[2], a[3], xb[2 * k], xb[2 * k + 1]);
            mma16816(c1, b[0], b[1], b[2], b[3], xb[2 * k + 2], xb[2 * k + 3]);
        }
        float4* redq = reinterpret_cast<float4*>(sptr + OFF_RED) + mt * 32 + lane;
        if (hf) *redq = make_float4(c0[0] + c1[0], c0[1] + c1[1], c0[2] + c1[2], c0[3] + c1[3]);
        bar_sync(2, 256);
        if (lane == 0) { mbar_arrive(bar_empty); mbar_arrive(bar_empty + 8); }
        if (!hf) {
            const float4 o = *redq;
            const uint32_t w0 = pair_rows(c0[0] + c1[0] + o.x, c0[2] + c1[2] + o.z, odd);
            const uint32_t w1 = pair_rows(c0[1] + c1[1] + o.y, c0[3] + c1[3] + o.w, odd);
            uint32_t* dst = reinterpret_cast<uint32_t*>(&g_qin[grp0 + t][0]) + rank * 32 + mt * 8 + (odd ? 4 : 0) + (g >> 1);
            st_pub(dst, w0);
            st_pub(dst + 4 * 256, w1);
        }
        bar_sync(4, 288);
    }
    {
        uint32_t qa[32];
        const uint32_t* q32 = reinterpret_cast<const uint32_t*>(sptr + OFF_Q + (g & 1) * 576);
#pragma unroll
        for (int k = 0; k < 16; k++) { qa[2 * k] = q32[8 * k + t]; qa[2 * k + 1] = q32[8 * k + 4 + t]; }
        const int key = warp * 8 + (lane & 7);
        const uint32_t off0 = key * 128 + ((((lane >> 3)) ^ (key & 7)) << 4);
        const uint32_t off1 = key * 128 + (((4 + (lane >> 3)) ^ (key & 7)) << 4);
        float2* sS = reinterpret_cast<float2*>(sptr + OFF_S) + (g & 1) * 512 + warp * 4 + t;
#pragma unroll 1
        for (int i = 0; i < NKT; i++) {
            mbar_wait(bar_full + 8 * slot, ph);
            const uint32_t base = sbase + OFF_RING + slot * TILE_BYTES;
            float c0[4] = {0.f, 0.f, 0.f, 0.f}, c1[4] = {0.f, 0.f, 0.f, 0.f};
            uint32_t kb[8][4];
#pragma unroll
            for (int c = 0; c < 4; c++) {
                ldsm4(kb[2 * c], base + c * 8192 + off0);
                ldsm4(kb[2 * c + 1], base + c * 8192 + off1);
            }
#pragma unroll
            for (int j = 0; j < 8; j++) {
                mma16816(c0, qa[4 * j], qa[4 * j], qa[4 * j + 1], qa[4 * j + 1], kb[j][0], kb[j][1]);
                mma16816(c1, qa[4 * j + 2], qa[4 * j + 2], qa[4 * j + 3], qa[4 * j + 3], kb[j][2], kb[j][3]);
            }
            if (g < 2) sS[i * 32] = make_float2(c0[0] + c1[0], c0[1] + c1[1]);
            __syncwarp();
            if (lane == 0) mbar_arrive(bar_empty + 8 * slot);
            if (++slot == RING) { slot = 0; ph ^= 1; }
        }
    }
    bar_sync(2, 256);
    {
        const int h = warp >> 2, j = tid & 127;
        const float4* sS = reinterpret_cast<const float4*>(sptr + OFF_S) + h * 256 + j * 2;
        float4 a = sS[0], b = sS[1];
        {
            const uint32_t r0 = pack_bf16(a.x, a.y), r1 = pack_bf16(a.z, a.w), r2 = pack_bf16(b.x, b.y), r3 = pack_bf16(b.z, b.w);
            a = make_float4(bf_lo(r0), bf_hi(r0), bf_lo(r1), bf_hi(r1));
            b = make_float4(bf_lo(r2), bf_hi(r2), bf_lo(r3), bf_hi(r3));
        }
        float m = fmaxf(fmaxf(fmaxf(a.x, a.y), fmaxf(a.z, a.w)), fmaxf(fmaxf(b.x, b.y), fmaxf(b.z, b.w)));
#pragma unroll
        for (int o = 16; o > 0; o >>= 1) m = fmaxf(m, __shfl_xor_sync(~0u, m, o));
        if (lane == 0) s_misc[warp] = m;
        bar_sync(2, 256);
        m = fmaxf(fmaxf(s_misc[h * 4], s_misc[h * 4 + 1]), fmaxf(s_misc[h * 4 + 2], s_misc[h * 4 + 3]));
        const uint32_t p0 = pack_bf16(exp2f((a.x - m) * SCALE_LOG2E), exp2f((a.y - m) * SCALE_LOG2E));
        const uint32_t p1 = pack_bf16(exp2f((a.z - m) * SCALE_LOG2E), exp2f((a.w - m) * SCALE_LOG2E));
        const uint32_t p2 = pack_bf16(exp2f((b.x - m) * SCALE_LOG2E), exp2f((b.y - m) * SCALE_LOG2E));
        const uint32_t p3 = pack_bf16(exp2f((b.z - m) * SCALE_LOG2E), exp2f((b.w - m) * SCALE_LOG2E));
        float l = (bf_lo(p0) + bf_hi(p0)) + (bf_lo(p1) + bf_hi(p1)) + (bf_lo(p2) + bf_hi(p2)) + (bf_lo(p3) + bf_hi(p3));
        uint32_t* sP = reinterpret_cast<uint32_t*>(sptr + OFF_P + h * P_STRIDE) + (j >> 3) * 32 + (j & 7);
        sP[0] = p0; sP[8] = p1; sP[16] = p2; sP[24] = p3;
#pragma unroll
        for (int o = 16; o > 0; o >>= 1) l += __shfl_xor_sync(~0u, l, o);
        if (lane == 0) { s_misc[8 + warp] = l; if ((warp & 3) == 0) s_misc[16 + h] = m; }
        bar_sync(2, 256);
        if (tid < 16) {
            const int dstj = tid >> 2, e = tid & 3, hh = e >> 1;
            const float val = (e & 1) ? (s_misc[8 + hh * 4] + s_misc[9 + hh * 4]) + (s_misc[10 + hh * 4] + s_misc[11 + hh * 4])
                                      : s_misc[16 + hh];
            mbar_wait(bar_ok, 0);
            st_pub(reinterpret_cast<uint32_t*>(&g_stat[grp0 + batch * 4 + dstj][split]) + e, __float_as_uint(val));
        }
        __syncwarp();
    }
    constexpr int WSLOT0 = (NTILES - 2) % RING, WSLOT1 = (NTILES - 1) % RING;
    static_assert((NTILES - 2) / RING == (NTILES - 1) / RING, "both wo tiles in the same ring round");
    uint32_t* odst;
    {
        const int pj = (warp & 1) * 16 + (t >> 1) * 8 + (odd ? 4 : 0) + (g >> 1);
        const int widx = rank * 32 + (pj & 3) * 8 + (pj >> 3) * 2 + ((pj >> 2) & 1);
        odst = reinterpret_cast<uint32_t*>(&g_oin[grp0 + (t & 1) * 4 + (warp >> 1)][0]) + widx;
    }
    float4* ydst = g_yacc + ((branch * 7 + warp) * 11 + (lane >> 2)) * 16 + (lane & 3);
    __nv_bfloat16* optr = out + branch * 448 + warp * 64;
    auto out_off = [](int l) { return ((l >> 1) & 1) * 896 + (l >> 2) + (l & 1) * 8; };
    int ooff = out_off(lane) | ((out_off(3 * lane) + 48) << 10);
    int ooff2 = (out_off(3 * lane + 1) + 48) | ((out_off(3 * lane + 2) + 48) << 10);
    uint32_t woff[4];
#pragma unroll
    for (int k = 0; k < 4; k++)
        woff[k] = sbase + OFF_RING + (warp < 4 ? WSLOT0 : WSLOT1) * TILE_BYTES + (warp & 3) * 8192 + krow * 128 + (((2 * k + ub) ^ (lane & 7)) << 4);
    uint32_t bar_w = bar_full + 8 * (warp < 4 ? WSLOT0 : WSLOT1);
    uint32_t baddr = sbase + OFF_B + lane * 16;
    asm volatile("" : "+l"(odst), "+l"(ydst), "+l"(optr), "+r"(woff[0]), "+r"(woff[1]), "+r"(woff[2]), "+r"(woff[3]),
                 "+r"(bar_w), "+r"(baddr), "+r"(ooff), "+r"(ooff2));

    float o0[4] = {0.f, 0.f, 0.f, 0.f}, o1[4] = {0.f, 0.f, 0.f, 0.f};
    float fnorm = 0.f;
    {
        const int u0 = (warp & 1) * 4 + ub;
        const uint32_t offa = (warp >> 1) * 8192 + krow * 128 + ((u0 ^ (lane & 7)) << 4);
        const uint32_t offb = (warp >> 1) * 8192 + krow * 128 + (((u0 + 2) ^ (lane & 7)) << 4);
        const uint4* sP = reinterpret_cast<const uint4*>(sptr + OFF_P + (g & 1) * P_STRIDE + t * 32);
#pragma unroll 1
        for (int i = 0; i < NKT; i++) {
            const uint4 pa = sP[i * 8], pb = sP[i * 8 + 1];
            if (i == NKT - 1) { mbar_wait(bar_stat, 0); fnorm = s_misc[32 + (t & 1)]; }
            mbar_wait(bar_full + 8 * slot, ph);
            const uint32_t base = sbase + OFF_RING + slot * TILE_BYTES;
            uint32_t va[8][4];
#pragma unroll
            for (int ks = 0; ks < 4; ks++) {
                ldsm4t(va[2 * ks], base + ks * 2048 + offa);
                ldsm4t(va[2 * ks + 1], base + ks * 2048 + offb);
            }
            const uint32_t pp[8] = {pa.x, pa.y, pa.z, pa.w, pb.x, pb.y, pb.z, pb.w};
#pragma unroll
            for (int ks = 0; ks < 4; ks++) {
                mma16816(o0, va[2 * ks][0], va[2 * ks][1], va[2 * ks][2], va[2 * ks][3], pp[2 * ks], pp[2 * ks + 1]);
                mma16816(o1, va[2 * ks + 1][0], va[2 * ks + 1][1], va[2 * ks + 1][2], va[2 * ks + 1][3], pp[2 * ks], pp[2 * ks + 1]);
            }
            __syncwarp();
            if (lane == 0) mbar_arrive(bar_empty + 8 * slot);
            if (tid == 0 && (i == STAT_AT || i == NKT - 1)) mbar_arrive(bar_go);
            if (++slot == RING) { slot = 0; ph ^= 1; }
        }
    }
    {
        const float lo = ((t & 2) ? (todd ? o1[1] : o1[0]) : (todd ? o0[1] : o0[0])) * fnorm;
        const float hi = ((t & 2) ? (todd ? o1[3] : o1[2]) : (todd ? o0[3] : o0[2])) * fnorm;
        st_pub(odst, pair_rows(lo, hi, odd));
    }
    if (warp == 7) return;

    uint32_t wa[16][4];
    uint4 b0, b1;
    mbar_wait(bar_w, ((NTILES - 1) / RING) & 1);
    const bool early = mbar_test(bar_b, 0);
    if (early) { b0 = lds128(baddr); b1 = lds128(baddr + 512); }
#pragma unroll
    for (int k = 0; k < 16; k++) ldsm4t(wa[k], woff[k & 3] + (k >> 2) * 2048);
    if (!early) {
        mbar_wait(bar_b, 0);
        b0 = lds128(baddr); b1 = lds128(baddr + 512);
    }
    const uint32_t bb[8] = {b0.x, b0.y, b0.z, b0.w, b1.x, b1.y, b1.z, b1.w};
    float y[8][4];
#pragma unroll
    for (int i = 0; i < 8; i++) { y[i][0] = y[i][1] = y[i][2] = y[i][3] = 0.f; }
#pragma unroll
    for (int k = 0; k < 16; k++)
        mma16816(y[k & 7], wa[k][0], wa[k][1], wa[k][2], wa[k][3], bb[2 * (k >> 2)], bb[2 * (k >> 2) + 1]);
    float val[4];
#pragma unroll
    for (int i = 3; i >= 0; i--) {
        const float v0 = (y[i][0] + y[i][1]) + (y[i + 4][0] + y[i + 4][1]);
        const float v1 = (y[i][2] + y[i][3]) + (y[i + 4][2] + y[i + 4][3]);
        val[i] = (todd ? v1 : v0) + __shfl_xor_sync(~0u, todd ? v0 : v1, 1);
    }
    const float u0 = __shfl_sync(~0u, val[3], 3 * lane), u1 = __shfl_sync(~0u, val[3], 3 * lane + 1);
    const float u2 = __shfl_sync(~0u, val[3], 3 * lane + 2);
    float4 oa, ob = make_float4(0.f, 0.f, 0.f, 0.f);
    atom_add4(oa, ydst, val[0], val[1], val[2]);
    if (lane < 11) atom_add4(ob, ydst + 8 * 16, u0, u1, u2);
    if (oa.w == 63.0f) {
        st_bf16(optr + (ooff & 1023), oa.x + val[0]);
        st_bf16(optr + (ooff & 1023) + 16, oa.y + val[1]);
        st_bf16(optr + (ooff & 1023) + 32, oa.z + val[2]);
    }
    if (ob.w == 63.0f) {
        st_bf16(optr + (ooff >> 10), ob.x + u0);
        st_bf16(optr + (ooff2 & 1023), ob.y + u1);
        if (lane < 10) st_bf16(optr + (ooff2 >> 10), ob.z + u2);
    }
}

__device__ float g_fq[2][2][4096], g_fo[2][2][4096];
struct Ptrs { const __nv_bfloat16* p[10]; };
__device__ __forceinline__ float rbf(float v) { return __bfloat162float(__float2bfloat16(v)); }

__global__ void fb_q(Ptrs in) {
    const int c = blockIdx.x * 256 + threadIdx.x, b = blockIdx.y, br = blockIdx.z;
    const __nv_bfloat16 *x = in.p[br * 5] + b * 448, *w = in.p[br * 5 + 3] + c;
    float a = 0.f;
    for (int k = 0; k < 448; k++) a += __bfloat162float(x[k]) * __bfloat162float(w[(size_t)k * 4096]);
    g_fq[br][b][c] = rbf(a);
}
__global__ void fb_attn(Ptrs in) {
    __shared__ float s[SK], q[256], red[8];
    const int h = blockIdx.x, b = blockIdx.y, br = blockIdx.z, tid = threadIdx.x;
    const size_t base = (size_t)(b * 8 + (h >> 1)) * SK * 256;
    const __nv_bfloat16 *K = in.p[br * 5 + 1] + base, *V = in.p[br * 5 + 2] + base;
    q[tid] = g_fq[br][b][h * 256 + tid];
    __syncthreads();
    float m = -INFINITY;
    for (int k = tid; k < SK; k += 256) {
        float a = 0.f;
        for (int d = 0; d < 256; d++) a += q[d] * __bfloat162float(K[(size_t)k * 256 + d]);
        s[k] = rbf(a);
        m = fmaxf(m, s[k]);
    }
    for (int o = 16; o > 0; o >>= 1) m = fmaxf(m, __shfl_xor_sync(~0u, m, o));
    if ((tid & 31) == 0) red[tid >> 5] = m;
    __syncthreads();
    for (int w = 0; w < 8; w++) m = fmaxf(m, red[w]);
    __syncthreads();
    float l = 0.f;
    for (int k = tid; k < SK; k += 256) { s[k] = exp2f((s[k] - m) * SCALE_LOG2E); l += s[k]; }
    for (int o = 16; o > 0; o >>= 1) l += __shfl_xor_sync(~0u, l, o);
    if ((tid & 31) == 0) red[tid >> 5] = l;
    __syncthreads();
    l = 0.f;
    for (int w = 0; w < 8; w++) l += red[w];
    float a = 0.f;
    for (int k = 0; k < SK; k++) a += rbf(s[k] / l) * __bfloat162float(V[(size_t)k * 256 + tid]);
    g_fo[br][b][h * 256 + tid] = rbf(a);
}
__global__ void fb_out(Ptrs in, __nv_bfloat16* out) {
    const int c = threadIdx.x, b = blockIdx.x, br = blockIdx.y;
    const __nv_bfloat16* w = in.p[br * 5 + 4] + c;
    float a = 0.f;
    for (int k = 0; k < 4096; k++) a += g_fo[br][b][k] * __bfloat162float(w[(size_t)k * 448]);
    out[b * 896 + br * 448 + c] = __float2bfloat16(a);
}

typedef CUresult (*EncodeFn)(CUtensorMap*, CUtensorMapDataType, cuuint32_t, void*, const cuuint64_t*,
                             const cuuint64_t*, const cuuint32_t*, const cuuint32_t*, CUtensorMapInterleave,
                             CUtensorMapSwizzle, CUtensorMapL2promotion, CUtensorMapFloatOOBfill);

void encode_map(EncodeFn fn, CUtensorMap* tm, const void* base, uint64_t rows, uint32_t chunks,
                uint32_t box_rows, uint32_t box_chunks) {
    cuuint64_t dims[3] = {64, rows, chunks};
    cuuint64_t strides[2] = {(cuuint64_t)chunks * 128, 128};
    cuuint32_t box[3] = {64, box_rows, box_chunks};
    cuuint32_t es[3] = {1, 1, 1};
    fn(tm, CU_TENSOR_MAP_DATA_TYPE_BFLOAT16, 3, const_cast<void*>(base), dims, strides, box, es,
       CU_TENSOR_MAP_INTERLEAVE_NONE, CU_TENSOR_MAP_SWIZZLE_128B, CU_TENSOR_MAP_L2_PROMOTION_L2_256B,
       CU_TENSOR_MAP_FLOAT_OOB_FILL_NONE);
}

}

extern "C" void kernel_launch(void* const* d_in, const int* in_sizes, int n_in, void* d_out, int out_size) {
    (void)in_sizes; (void)n_in; (void)out_size;
    static EncodeFn encode = nullptr;
    static int fused = -1;
    if (fused < 0) {
        void* fn = nullptr;
        cudaDriverEntryPointQueryResult st;
        cudaGetDriverEntryPoint("cuTensorMapEncodeTiled", &fn, cudaEnableDefault, &st);
        encode = reinterpret_cast<EncodeFn>(fn);
        cudaFuncSetAttribute(gqa_decode_kernel, cudaFuncAttributeMaxDynamicSharedMemorySize, SMEM_BYTES);
        int dev = 0, sms = 0, per_sm = 0;
        cudaGetDevice(&dev);
        cudaDeviceGetAttribute(&sms, cudaDevAttrMultiProcessorCount, dev);
        cudaOccupancyMaxActiveBlocksPerMultiprocessor(&per_sm, gqa_decode_kernel, NTHREADS, SMEM_BYTES);
        fused = encode && sms * per_sm >= NCTA;
    }
    if (!fused) {
        Ptrs in;
        for (int i = 0; i < 10; i++) in.p[i] = static_cast<const __nv_bfloat16*>(d_in[i]);
        fb_q<<<dim3(16, 2, 2), 256>>>(in);
        fb_attn<<<dim3(16, 2, 2), 256>>>(in);
        fb_out<<<dim3(2, 2), 448>>>(in, static_cast<__nv_bfloat16*>(d_out));
        return;
    }
    Maps m;
    for (int br = 0; br < 2; br++) {
        encode_map(encode, &m.tm[br * 5 + 0], d_in[br * 5 + 3], 448, 64, 224, 1);
        encode_map(encode, &m.tm[br * 5 + 1], d_in[br * 5 + 1], 2 * 8 * SK, 4, TILE_KEYS, 4);
        encode_map(encode, &m.tm[br * 5 + 2], d_in[br * 5 + 2], 2 * 8 * SK, 4, TILE_KEYS, 4);
        encode_map(encode, &m.tm[br * 5 + 3], d_in[br * 5 + 4], 4096, 7, 64, 4);
        encode_map(encode, &m.tm[br * 5 + 4], d_in[br * 5 + 4], 4096, 7, 64, 3);
    }
    gqa_decode_kernel<<<NCTA, NTHREADS, SMEM_BYTES>>>(
        static_cast<const __nv_bfloat16*>(d_in[0]), static_cast<const __nv_bfloat16*>(d_in[5]),
        static_cast<__nv_bfloat16*>(d_out),
        m);
}
```
